```python
import torch

def _softmax(x, axis=-1):
    return torch.softmax(x, dim=axis)
def _gelu(x):
    return torch.nn.functional.gelu(x, approximate="tanh")
def _silu(x):
    return torch.nn.functional.silu(x)
def _sigmoid(x):
    return torch.sigmoid(x)
def _layernorm(x, axis=-1, eps=1e-5):
    m = x.mean(dim=axis, keepdim=True)
    v = x.var(dim=axis, keepdim=True, unbiased=False)
    return (x - m) / torch.sqrt(v + eps)
def _scatter_add(tgt, idx, src, axis=0):
    return tgt.clone().index_add_(axis, idx, src)
def _segment_sum(src, seg, n):
    out = torch.zeros((n,) + src.shape[1:], dtype=src.dtype)
    return out.index_add_(0, seg, src)
def _pad(x, pw):
    flat = tuple(v for pair in reversed(pw) for v in pair)
    return torch.nn.functional.pad(x, flat)

kernel_name = 'concat_heads__sliding_local_dilated__sliding_local_dilated__prompt'

def setup_inputs():

    _w = (lambda a: (lambda t: t.to(torch.bfloat16) if t.is_floating_point() else t)(torch.as_tensor(a)))
    def _A_setup():
        B, S, D = 1, 2048, 1024
        return {
            "x": _w((lambda *s: torch.randn(*s, dtype=torch.bfloat16) * 0.2)(B, S, D)),
            "wqkv": _w((lambda *s: torch.randn(*s, dtype=torch.bfloat16) * 0.2)(D, 3 * D)),
            "wo": _w((lambda *s: torch.randn(*s, dtype=torch.bfloat16) * 0.05)(D, D)),
        }
    _A_in = _A_setup()

    def _B_setup():
        B, S, D = 1, 2048, 1024
        return {
            "x": _w((lambda *s: torch.randn(*s, dtype=torch.bfloat16) * 0.2)(B, S, D)),
            "wqkv": _w((lambda *s: torch.randn(*s, dtype=torch.bfloat16) * 0.2)(D, 3 * D)),
            "wo": _w((lambda *s: torch.randn(*s, dtype=torch.bfloat16) * 0.05)(D, D)),
        }
    _B_in = _B_setup()

    return {
        "A_x": _A_in["x"],
        "A_wqkv": _A_in["wqkv"],
        "A_wo": _A_in["wo"],
        "B_x": _B_in["x"],
        "B_wqkv": _B_in["wqkv"],
        "B_wo": _B_in["wo"],
    }

def reference(A_x, A_wqkv, A_wo, B_x, B_wqkv, B_wo):
    def _A_ref(x, wqkv, wo):
        B, S, D = x.shape
        H = 32; Dh = D // H
        W, dil = 8, 2
        qkv = (lambda x, *d: x.permute(*d))((x @ wqkv).reshape(B, S, 3, H, Dh), 2, 0, 3, 1, 4)
        q, k, v = qkv[0], qkv[1], qkv[2]
        scale = Dh ** -0.5
        pos = torch.arange(S)
        off = torch.arange(W) * dil
        idx = pos[:, None] - off[None, :]
        mask = idx >= 0
        idx_c = torch.where(mask, idx, 0).reshape(-1)
        kg = k[:, :, idx_c, :].reshape(B, H, S, W, Dh)
        vg = v[:, :, idx_c, :].reshape(B, H, S, W, Dh)
        logits = torch.einsum("bhsd,bhswd->bhsw", q, kg) * scale
        logits = torch.where(mask[None, None, :, :], logits, -1e9)
        attn = _softmax(logits, axis=-1)
        o = torch.einsum("bhsw,bhswd->bhsd", attn, vg)
        return (lambda x, *d: x.permute(*d))(o, 0, 2, 1, 3).reshape(B, S, D) @ wo

    def _B_ref(x, wqkv, wo):
        B, S, D = x.shape
        H = 32; Dh = D // H
        W, dil = 8, 2
        qkv = (lambda x, *d: x.permute(*d))((x @ wqkv).reshape(B, S, 3, H, Dh), 2, 0, 3, 1, 4)
        q, k, v = qkv[0], qkv[1], qkv[2]
        scale = Dh ** -0.5
        pos = torch.arange(S)
        off = torch.arange(W) * dil
        idx = pos[:, None] - off[None, :]
        mask = idx >= 0
        idx_c = torch.where(mask, idx, 0).reshape(-1)
        kg = k[:, :, idx_c, :].reshape(B, H, S, W, Dh)
        vg = v[:, :, idx_c, :].reshape(B, H, S, W, Dh)
        logits = torch.einsum("bhsd,bhswd->bhsw", q, kg) * scale
        logits = torch.where(mask[None, None, :, :], logits, -1e9)
        attn = _softmax(logits, axis=-1)
        o = torch.einsum("bhsw,bhswd->bhsd", attn, vg)
        return (lambda x, *d: x.permute(*d))(o, 0, 2, 1, 3).reshape(B, S, D) @ wo

    a = _A_ref(A_x, A_wqkv, A_wo)
    b = _B_ref(B_x, B_wqkv, B_wo)
    return torch.concatenate([a, b], axis=-1)
```

```cpp
#include <cuda_runtime.h>
#include <cuda_bf16.h>
#include <cuda.h>
#include <stdint.h>

#define DEVI __device__ __forceinline__

namespace {

constexpr int NCTA = 128;
constexpr int STAGE = 49152, STAGES = 4;
constexpr int O_OFF = STAGE * STAGES;
constexpr int KX_OFF = O_OFF + 16384;
constexpr int VH_OFF = KX_OFF + 8192;
constexpr int BAR_OFF = O_OFF + 32768;
constexpr int SMEM_BYTES = BAR_OFF + 256;
static_assert(SMEM_BYTES <= 232448 && VH_OFF + 2048 <= BAR_OFF, "smem");
constexpr uint32_t B_FULL = 0, B_EMPTY = 32, B_XBAR = 64, B_OFULL = 128, B_OEMPTY = 144, B_EPOCH = 160, EPOCH_SLOT = 168, SINK = 176,
                   B_LAST = 184, B_OREADY = 192, B_OSENT = 224;
constexpr int REG_MMA = 224, REG_AUX = 56;
constexpr float LOG2E = 1.4426950408889634f;

struct Maps {
  CUtensorMap x[2], wqkv[2], wo[2], wo_half[2], o_ld, o_st, out;
};

__device__ __align__(1024) __nv_bfloat16 g_o[4096 * 1024];
__device__ __align__(128) uint4 g_halo[32 * 16 * 2 * 192];
__device__ __align__(128) unsigned g_o_flag[32 * 16];
__device__ unsigned long long g_ticket;

DEVI uint32_t smem_u32(const void* p) { return (uint32_t)__cvta_generic_to_shared(p); }
DEVI void mbar_init(uint32_t bar, uint32_t cnt) { asm volatile("mbarrier.init.shared::cta.b64 [%0], %1;" ::"r"(bar), "r"(cnt) : "memory"); }
DEVI void mbar_init_fence() { asm volatile("fence.mbarrier_init.release.cluster;" ::: "memory"); }
DEVI void mbar_expect_tx(uint32_t bar, uint32_t bytes) { asm volatile("mbarrier.arrive.expect_tx.shared::cta.b64 _, [%0], %1;" ::"r"(bar), "r"(bytes) : "memory"); }
DEVI void mbar_arrive(uint32_t bar) { asm volatile("mbarrier.arrive.shared::cta.b64 _, [%0];" ::"r"(bar) : "memory"); }
DEVI void mbar_wait(uint32_t bar, uint32_t parity) {
  asm volatile(
      "{\n.reg .pred p;\n.reg .u32 n;\nmov.u32 n, 0;\n"
      "WAIT_LOOP_%=:\n"
      "mbarrier.try_wait.parity.shared::cta.b64 p, [%0], %1;\n"
      "@p bra WAIT_DONE_%=;\n"
      "add.u32 n, n, 1;\n"
      "setp.lt.u32 p, n, 1048576;\n"
      "@p bra WAIT_LOOP_%=;\n"
      "trap;\n"
      "WAIT_DONE_%=:\n}" ::"r"(bar), "r"(parity) : "memory");
}
DEVI void tma_load_2d(uint32_t dst, const CUtensorMap* m, uint32_t bar, int c0, int c1) {
  asm volatile("cp.async.bulk.tensor.2d.shared::cluster.global.mbarrier::complete_tx::bytes [%0], [%1, {%3, %4}], [%2];"
               ::"r"(dst), "l"(m), "r"(bar), "r"(c0), "r"(c1) : "memory");
}
DEVI void tma_load_3d(uint32_t dst, const CUtensorMap* m, uint32_t bar, int c0, int c1, int c2) {
  asm volatile("cp.async.bulk.tensor.3d.shared::cluster.global.mbarrier::complete_tx::bytes [%0], [%1, {%3, %4, %5}], [%2];"
               ::"r"(dst), "l"(m), "r"(bar), "r"(c0), "r"(c1), "r"(c2) : "memory");
}
DEVI void tma_store_2d(const CUtensorMap* m, uint32_t src, int c0, int c1) {
  asm volatile("cp.async.bulk.tensor.2d.global.shared::cta.bulk_group [%0, {%2, %3}], [%1];" ::"l"(m), "r"(src), "r"(c0), "r"(c1) : "memory");
}
DEVI void tma_store_3d(const CUtensorMap* m, uint32_t src, int c0, int c1, int c2) {
  asm volatile("cp.async.bulk.tensor.3d.global.shared::cta.bulk_group [%0, {%2, %3, %4}], [%1];" ::"l"(m), "r"(src), "r"(c0), "r"(c1), "r"(c2) : "memory");
}
DEVI void bulk_commit() { asm volatile("cp.async.bulk.commit_group;" ::: "memory"); }
DEVI void bulk_wait_all() { asm volatile("cp.async.bulk.wait_group 0;" ::: "memory"); }
DEVI void bulk_wait_read() { asm volatile("cp.async.bulk.wait_group.read 0;" ::: "memory"); }
DEVI void prefetch_map(const CUtensorMap* m) { asm volatile("prefetch.tensormap [%0];" ::"l"(m) : "memory"); }
DEVI void fence_async_smem() { asm volatile("fence.proxy.async.shared::cta;" ::: "memory"); }
DEVI void fence_async_global() { asm volatile("fence.proxy.async.global;" ::: "memory"); }
DEVI void named_sync(int id, int n) { asm volatile("bar.sync %0, %1;" ::"r"(id), "r"(n) : "memory"); }
DEVI void named_arrive(int id, int n) { asm volatile("bar.arrive %0, %1;" ::"r"(id), "r"(n) : "memory"); }
DEVI void named_sync_after(int id, int n, uint32_t dep) {
  asm volatile("{\n.reg .pred p, q;\nsetp.eq.u32 p, %2, 0;\nbarrier.cta.red.or.pred.aligned q, %0, %1, p;\n}" ::"r"(id), "r"(n), "r"(dep) : "memory");
}
DEVI bool elect_one() {
  uint32_t p;
  asm volatile("{\n.reg .pred q;\nelect.sync _|q, 0xffffffff;\nselp.u32 %0, 1, 0, q;\n}" : "=r"(p));
  return p != 0;
}
DEVI void wgmma_fence() { asm volatile("wgmma.fence.sync.aligned;" ::: "memory"); }
DEVI void wgmma_commit() { asm volatile("wgmma.commit_group.sync.aligned;" ::: "memory"); }
template <int N> DEVI void wgmma_wait() { asm volatile("wgmma.wait_group.sync.aligned %0;" ::"n"(N) : "memory"); }
DEVI uint32_t desc_lo(uint32_t addr, uint32_t lbo_bytes) { return ((addr & 0x3FFFF) >> 4) | ((lbo_bytes >> 4) << 16); }
template <int NR> DEVI void fence_acc(float (&d)[NR]) {
#pragma unroll
  for (int i = 0; i < NR; i++) asm volatile("" : "+f"(d[i])::"memory");
}
DEVI uint32_t pack_bf16(float lo, float hi) {
  uint32_t r;
  asm("cvt.rn.bf16x2.f32 %0, %1, %2;" : "=r"(r) : "f"(hi), "f"(lo));
  return r;
}
DEVI void stsm_x4(uint32_t addr, uint32_t r0, uint32_t r1, uint32_t r2, uint32_t r3) {
  asm volatile("stmatrix.sync.aligned.m8n8.x4.shared.b16 [%0], {%1, %2, %3, %4};" ::"r"(addr), "r"(r0), "r"(r1), "r"(r2), "r"(r3) : "memory");
}
DEVI void stsm_x4_t(uint32_t addr, uint32_t r0, uint32_t r1, uint32_t r2, uint32_t r3) {
  asm volatile("stmatrix.sync.aligned.m8n8.x4.trans.shared.b16 [%0], {%1, %2, %3, %4};" ::"r"(addr), "r"(r0), "r"(r1), "r"(r2), "r"(r3) : "memory");
}
DEVI void ldsm_x4(uint32_t addr, uint32_t* r) {
  asm volatile("ldmatrix.sync.aligned.m8n8.x4.shared.b16 {%0, %1, %2, %3}, [%4];" : "=r"(r[0]), "=r"(r[1]), "=r"(r[2]), "=r"(r[3]) : "r"(addr) : "memory");
}
DEVI void ldsm_x4_t(uint32_t addr, uint32_t* r) {
  asm volatile("ldmatrix.sync.aligned.m8n8.x4.trans.shared.b16 {%0, %1, %2, %3}, [%4];" : "=r"(r[0]), "=r"(r[1]), "=r"(r[2]), "=r"(r[3]) : "r"(addr) : "memory");
}
DEVI void mma_16816(float (&c)[4], uint32_t a0, uint32_t a1, uint32_t a2, uint32_t a3, uint32_t b0, uint32_t b1) {
  asm volatile("mma.sync.aligned.m16n8k16.row.col.f32.bf16.bf16.f32 {%0,%1,%2,%3}, {%4,%5,%6,%7}, {%8,%9}, {%10,%10,%10,%10};"
               : "=f"(c[0]), "=f"(c[1]), "=f"(c[2]), "=f"(c[3]) : "r"(a0), "r"(a1), "r"(a2), "r"(a3), "r"(b0), "r"(b1), "f"(0.f));
}
DEVI uint32_t movm_t(uint32_t a) {
  uint32_t d;
  asm volatile("movmatrix.sync.aligned.m8n8.trans.b16 %0, %1;" : "=r"(d) : "r"(a));
  return d;
}
DEVI void st_pkt(uint4* p, uint32_t a, uint32_t b, uint32_t c, uint32_t tag) {
  asm volatile("{\n.reg .b128 v;\nmov.b128 v, {%1, %2, %3, %4};\nst.relaxed.gpu.global.b128 [%0], v;\n}" ::"l"(p), "r"(a), "r"(b), "r"(c), "r"(tag) : "memory");
}
DEVI uint4 ld_pkt(const uint4* p) {
  uint4 r;
  asm volatile("{\n.reg .b128 v;\nld.relaxed.gpu.global.b128 v, [%4];\nmov.b128 {%0, %1, %2, %3}, v;\n}" : "=r"(r.x), "=r"(r.y), "=r"(r.z), "=r"(r.w) : "l"(p) : "memory");
  return r;
}
DEVI unsigned ld_acquire(const unsigned* p) {
  unsigned v;
  asm volatile("ld.acquire.gpu.global.u32 %0, [%1];" : "=r"(v) : "l"(p) : "memory");
  return v;
}
DEVI void red_add(unsigned* p, unsigned v) { asm volatile("red.relaxed.gpu.global.add.u32 [%0], %1;" ::"l"(p), "r"(v) : "memory"); }
DEVI uint32_t lds32(uint32_t addr) {
  uint32_t v;
  asm volatile("ld.shared.u32 %0, [%1];" : "=r"(v) : "r"(addr) : "memory");
  return v;
}
DEVI uint32_t scale_logits(uint32_t x) {
  uint32_t d;
  asm("{\n.reg .b32 t;\nmul.rn.bf16x2 t, %1, %3;\nfma.rn.bf16x2 %0, %1, %2, t;\n}" : "=r"(d) : "r"(x), "r"(0x3e353e35u), "r"(0x379e379eu));
  return d;
}
DEVI float bf_lo(uint32_t w) { return __uint_as_float(w << 16); }
DEVI float bf_hi(uint32_t w) { return __uint_as_float(w & 0xffff0000u); }
DEVI float rcp(float x) { float y; asm("rcp.approx.ftz.f32 %0, %1;" : "=f"(y) : "f"(x)); return y; }
DEVI float ex2(float x) { float y; asm("ex2.approx.ftz.f32 %0, %1;" : "=f"(y) : "f"(x)); return y; }

template <int OA, int OB> DEVI void wgmma_set(float (&d)[96], uint32_t da, uint32_t db) {
  asm volatile("{\n.reg .pred p;\n.reg .b32 la, lb;\n.reg .b64 da, db;\nsetp.ne.b32 p, 0, 0;\n"
    "add.u32 la, %96, %98;\nadd.u32 lb, %97, %99;\nmov.b64 da, {la, 0x40000040};\nmov.b64 db, {lb, 0x40000040};\n"
    "wgmma.mma_async.sync.aligned.m64n192k16.f32.bf16.bf16 {"
    "%0,%1,%2,%3,%4,%5,%6,%7,%8,%9,%10,%11,%12,%13,%14,%15,"
    "%16,%17,%18,%19,%20,%21,%22,%23,%24,%25,%26,%27,%28,%29,%30,%31,"
    "%32,%33,%34,%35,%36,%37,%38,%39,%40,%41,%42,%43,%44,%45,%46,%47,"
    "%48,%49,%50,%51,%52,%53,%54,%55,%56,%57,%58,%59,%60,%61,%62,%63,"
    "%64,%65,%66,%67,%68,%69,%70,%71,%72,%73,%74,%75,%76,%77,%78,%79,"
    "%80,%81,%82,%83,%84,%85,%86,%87,%88,%89,%90,%91,%92,%93,%94,%95"
    "}, da, db, p, 1, 1, 0, 1;\n}"
    : "=f"(d[0]), "=f"(d[1]), "=f"(d[2]), "=f"(d[3]), "=f"(d[4]), "=f"(d[5]), "=f"(d[6]), "=f"(d[7]),
      "=f"(d[8]), "=f"(d[9]), "=f"(d[10]), "=f"(d[11]), "=f"(d[12]), "=f"(d[13]), "=f"(d[14]), "=f"(d[15]),
      "=f"(d[16]), "=f"(d[17]), "=f"(d[18]), "=f"(d[19]), "=f"(d[20]), "=f"(d[21]), "=f"(d[22]), "=f"(d[23]),
      "=f"(d[24]), "=f"(d[25]), "=f"(d[26]), "=f"(d[27]), "=f"(d[28]), "=f"(d[29]), "=f"(d[30]), "=f"(d[31]),
      "=f"(d[32]), "=f"(d[33]), "=f"(d[34]), "=f"(d[35]), "=f"(d[36]), "=f"(d[37]), "=f"(d[38]), "=f"(d[39]),
      "=f"(d[40]), "=f"(d[41]), "=f"(d[42]), "=f"(d[43]), "=f"(d[44]), "=f"(d[45]), "=f"(d[46]), "=f"(d[47]),
      "=f"(d[48]), "=f"(d[49]), "=f"(d[50]), "=f"(d[51]), "=f"(d[52]), "=f"(d[53]), "=f"(d[54]), "=f"(d[55]),
      "=f"(d[56]), "=f"(d[57]), "=f"(d[58]), "=f"(d[59]), "=f"(d[60]), "=f"(d[61]), "=f"(d[62]), "=f"(d[63]),
      "=f"(d[64]), "=f"(d[65]), "=f"(d[66]), "=f"(d[67]), "=f"(d[68]), "=f"(d[69]), "=f"(d[70]), "=f"(d[71]),
      "=f"(d[72]), "=f"(d[73]), "=f"(d[74]), "=f"(d[75]), "=f"(d[76]), "=f"(d[77]), "=f"(d[78]), "=f"(d[79]),
      "=f"(d[80]), "=f"(d[81]), "=f"(d[82]), "=f"(d[83]), "=f"(d[84]), "=f"(d[85]), "=f"(d[86]), "=f"(d[87]),
      "=f"(d[88]), "=f"(d[89]), "=f"(d[90]), "=f"(d[91]), "=f"(d[92]), "=f"(d[93]), "=f"(d[94]), "=f"(d[95])
    : "r"(da), "r"(db), "n"(OA), "n"(OB));
}

template <int OA, int OB> DEVI void wgmma_acc(float (&d)[96], uint32_t da, uint32_t db) {
  asm volatile("{\n.reg .pred p;\n.reg .b32 la, lb;\n.reg .b64 da, db;\nsetp.ne.b32 p, 1, 0;\n"
    "add.u32 la, %96, %98;\nadd.u32 lb, %97, %99;\nmov.b64 da, {la, 0x40000040};\nmov.b64 db, {lb, 0x40000040};\n"
    "wgmma.mma_async.sync.aligned.m64n192k16.f32.bf16.bf16 {"
    "%0,%1,%2,%3,%4,%5,%6,%7,%8,%9,%10,%11,%12,%13,%14,%15,"
    "%16,%17,%18,%19,%20,%21,%22,%23,%24,%25,%26,%27,%28,%29,%30,%31,"
    "%32,%33,%34,%35,%36,%37,%38,%39,%40,%41,%42,%43,%44,%45,%46,%47,"
    "%48,%49,%50,%51,%52,%53,%54,%55,%56,%57,%58,%59,%60,%61,%62,%63,"
    "%64,%65,%66,%67,%68,%69,%70,%71,%72,%73,%74,%75,%76,%77,%78,%79,"
    "%80,%81,%82,%83,%84,%85,%86,%87,%88,%89,%90,%91,%92,%93,%94,%95"
    "}, da, db, p, 1, 1, 0, 1;\n}"
    : "+f"(d[0]), "+f"(d[1]), "+f"(d[2]), "+f"(d[3]), "+f"(d[4]), "+f"(d[5]), "+f"(d[6]), "+f"(d[7]),
      "+f"(d[8]), "+f"(d[9]), "+f"(d[10]), "+f"(d[11]), "+f"(d[12]), "+f"(d[13]), "+f"(d[14]), "+f"(d[15]),
      "+f"(d[16]), "+f"(d[17]), "+f"(d[18]), "+f"(d[19]), "+f"(d[20]), "+f"(d[21]), "+f"(d[22]), "+f"(d[23]),
      "+f"(d[24]), "+f"(d[25]), "+f"(d[26]), "+f"(d[27]), "+f"(d[28]), "+f"(d[29]), "+f"(d[30]), "+f"(d[31]),
      "+f"(d[32]), "+f"(d[33]), "+f"(d[34]), "+f"(d[35]), "+f"(d[36]), "+f"(d[37]), "+f"(d[38]), "+f"(d[39]),
      "+f"(d[40]), "+f"(d[41]), "+f"(d[42]), "+f"(d[43]), "+f"(d[44]), "+f"(d[45]), "+f"(d[46]), "+f"(d[47]),
      "+f"(d[48]), "+f"(d[49]), "+f"(d[50]), "+f"(d[51]), "+f"(d[52]), "+f"(d[53]), "+f"(d[54]), "+f"(d[55]),
      "+f"(d[56]), "+f"(d[57]), "+f"(d[58]), "+f"(d[59]), "+f"(d[60]), "+f"(d[61]), "+f"(d[62]), "+f"(d[63]),
      "+f"(d[64]), "+f"(d[65]), "+f"(d[66]), "+f"(d[67]), "+f"(d[68]), "+f"(d[69]), "+f"(d[70]), "+f"(d[71]),
      "+f"(d[72]), "+f"(d[73]), "+f"(d[74]), "+f"(d[75]), "+f"(d[76]), "+f"(d[77]), "+f"(d[78]), "+f"(d[79]),
      "+f"(d[80]), "+f"(d[81]), "+f"(d[82]), "+f"(d[83]), "+f"(d[84]), "+f"(d[85]), "+f"(d[86]), "+f"(d[87]),
      "+f"(d[88]), "+f"(d[89]), "+f"(d[90]), "+f"(d[91]), "+f"(d[92]), "+f"(d[93]), "+f"(d[94]), "+f"(d[95])
    : "r"(da), "r"(db), "n"(OA), "n"(OB));
}

template <int OA, int OB> DEVI void wgmma_set(float (&d)[128], uint32_t da, uint32_t db) {
  asm volatile("{\n.reg .pred p;\n.reg .b32 la, lb;\n.reg .b64 da, db;\nsetp.ne.b32 p, 0, 0;\n"
    "add.u32 la, %128, %130;\nadd.u32 lb, %129, %131;\nmov.b64 da, {la, 0x40000040};\nmov.b64 db, {lb, 0x40000040};\n"
    "wgmma.mma_async.sync.aligned.m64n256k16.f32.bf16.bf16 {"
    "%0,%1,%2,%3,%4,%5,%6,%7,%8,%9,%10,%11,%12,%13,%14,%15,"
    "%16,%17,%18,%19,%20,%21,%22,%23,%24,%25,%26,%27,%28,%29,%30,%31,"
    "%32,%33,%34,%35,%36,%37,%38,%39,%40,%41,%42,%43,%44,%45,%46,%47,"
    "%48,%49,%50,%51,%52,%53,%54,%55,%56,%57,%58,%59,%60,%61,%62,%63,"
    "%64,%65,%66,%67,%68,%69,%70,%71,%72,%73,%74,%75,%76,%77,%78,%79,"
    "%80,%81,%82,%83,%84,%85,%86,%87,%88,%89,%90,%91,%92,%93,%94,%95,"
    "%96,%97,%98,%99,%100,%101,%102,%103,%104,%105,%106,%107,%108,%109,%110,%111,"
    "%112,%113,%114,%115,%116,%117,%118,%119,%120,%121,%122,%123,%124,%125,%126,%127"
    "}, da, db, p, 1, 1, 0, 1;\n}"
    : "=f"(d[0]), "=f"(d[1]), "=f"(d[2]), "=f"(d[3]), "=f"(d[4]), "=f"(d[5]), "=f"(d[6]), "=f"(d[7]),
      "=f"(d[8]), "=f"(d[9]), "=f"(d[10]), "=f"(d[11]), "=f"(d[12]), "=f"(d[13]), "=f"(d[14]), "=f"(d[15]),
      "=f"(d[16]), "=f"(d[17]), "=f"(d[18]), "=f"(d[19]), "=f"(d[20]), "=f"(d[21]), "=f"(d[22]), "=f"(d[23]),
      "=f"(d[24]), "=f"(d[25]), "=f"(d[26]), "=f"(d[27]), "=f"(d[28]), "=f"(d[29]), "=f"(d[30]), "=f"(d[31]),
      "=f"(d[32]), "=f"(d[33]), "=f"(d[34]), "=f"(d[35]), "=f"(d[36]), "=f"(d[37]), "=f"(d[38]), "=f"(d[39]),
      "=f"(d[40]), "=f"(d[41]), "=f"(d[42]), "=f"(d[43]), "=f"(d[44]), "=f"(d[45]), "=f"(d[46]), "=f"(d[47]),
      "=f"(d[48]), "=f"(d[49]), "=f"(d[50]), "=f"(d[51]), "=f"(d[52]), "=f"(d[53]), "=f"(d[54]), "=f"(d[55]),
      "=f"(d[56]), "=f"(d[57]), "=f"(d[58]), "=f"(d[59]), "=f"(d[60]), "=f"(d[61]), "=f"(d[62]), "=f"(d[63]),
      "=f"(d[64]), "=f"(d[65]), "=f"(d[66]), "=f"(d[67]), "=f"(d[68]), "=f"(d[69]), "=f"(d[70]), "=f"(d[71]),
      "=f"(d[72]), "=f"(d[73]), "=f"(d[74]), "=f"(d[75]), "=f"(d[76]), "=f"(d[77]), "=f"(d[78]), "=f"(d[79]),
      "=f"(d[80]), "=f"(d[81]), "=f"(d[82]), "=f"(d[83]), "=f"(d[84]), "=f"(d[85]), "=f"(d[86]), "=f"(d[87]),
      "=f"(d[88]), "=f"(d[89]), "=f"(d[90]), "=f"(d[91]), "=f"(d[92]), "=f"(d[93]), "=f"(d[94]), "=f"(d[95]),
      "=f"(d[96]), "=f"(d[97]), "=f"(d[98]), "=f"(d[99]), "=f"(d[100]), "=f"(d[101]), "=f"(d[102]), "=f"(d[103]),
      "=f"(d[104]), "=f"(d[105]), "=f"(d[106]), "=f"(d[107]), "=f"(d[108]), "=f"(d[109]), "=f"(d[110]), "=f"(d[111]),
      "=f"(d[112]), "=f"(d[113]), "=f"(d[114]), "=f"(d[115]), "=f"(d[116]), "=f"(d[117]), "=f"(d[118]), "=f"(d[119]),
      "=f"(d[120]), "=f"(d[121]), "=f"(d[122]), "=f"(d[123]), "=f"(d[124]), "=f"(d[125]), "=f"(d[126]), "=f"(d[127])
    : "r"(da), "r"(db), "n"(OA), "n"(OB));
}

template <int OA, int OB> DEVI void wgmma_acc(float (&d)[128], uint32_t da, uint32_t db) {
  asm volatile("{\n.reg .pred p;\n.reg .b32 la, lb;\n.reg .b64 da, db;\nsetp.ne.b32 p, 1, 0;\n"
    "add.u32 la, %128, %130;\nadd.u32 lb, %129, %131;\nmov.b64 da, {la, 0x40000040};\nmov.b64 db, {lb, 0x40000040};\n"
    "wgmma.mma_async.sync.aligned.m64n256k16.f32.bf16.bf16 {"
    "%0,%1,%2,%3,%4,%5,%6,%7,%8,%9,%10,%11,%12,%13,%14,%15,"
    "%16,%17,%18,%19,%20,%21,%22,%23,%24,%25,%26,%27,%28,%29,%30,%31,"
    "%32,%33,%34,%35,%36,%37,%38,%39,%40,%41,%42,%43,%44,%45,%46,%47,"
    "%48,%49,%50,%51,%52,%53,%54,%55,%56,%57,%58,%59,%60,%61,%62,%63,"
    "%64,%65,%66,%67,%68,%69,%70,%71,%72,%73,%74,%75,%76,%77,%78,%79,"
    "%80,%81,%82,%83,%84,%85,%86,%87,%88,%89,%90,%91,%92,%93,%94,%95,"
    "%96,%97,%98,%99,%100,%101,%102,%103,%104,%105,%106,%107,%108,%109,%110,%111,"
    "%112,%113,%114,%115,%116,%117,%118,%119,%120,%121,%122,%123,%124,%125,%126,%127"
    "}, da, db, p, 1, 1, 0, 1;\n}"
    : "+f"(d[0]), "+f"(d[1]), "+f"(d[2]), "+f"(d[3]), "+f"(d[4]), "+f"(d[5]), "+f"(d[6]), "+f"(d[7]),
      "+f"(d[8]), "+f"(d[9]), "+f"(d[10]), "+f"(d[11]), "+f"(d[12]), "+f"(d[13]), "+f"(d[14]), "+f"(d[15]),
      "+f"(d[16]), "+f"(d[17]), "+f"(d[18]), "+f"(d[19]), "+f"(d[20]), "+f"(d[21]), "+f"(d[22]), "+f"(d[23]),
      "+f"(d[24]), "+f"(d[25]), "+f"(d[26]), "+f"(d[27]), "+f"(d[28]), "+f"(d[29]), "+f"(d[30]), "+f"(d[31]),
      "+f"(d[32]), "+f"(d[33]), "+f"(d[34]), "+f"(d[35]), "+f"(d[36]), "+f"(d[37]), "+f"(d[38]), "+f"(d[39]),
      "+f"(d[40]), "+f"(d[41]), "+f"(d[42]), "+f"(d[43]), "+f"(d[44]), "+f"(d[45]), "+f"(d[46]), "+f"(d[47]),
      "+f"(d[48]), "+f"(d[49]), "+f"(d[50]), "+f"(d[51]), "+f"(d[52]), "+f"(d[53]), "+f"(d[54]), "+f"(d[55]),
      "+f"(d[56]), "+f"(d[57]), "+f"(d[58]), "+f"(d[59]), "+f"(d[60]), "+f"(d[61]), "+f"(d[62]), "+f"(d[63]),
      "+f"(d[64]), "+f"(d[65]), "+f"(d[66]), "+f"(d[67]), "+f"(d[68]), "+f"(d[69]), "+f"(d[70]), "+f"(d[71]),
      "+f"(d[72]), "+f"(d[73]), "+f"(d[74]), "+f"(d[75]), "+f"(d[76]), "+f"(d[77]), "+f"(d[78]), "+f"(d[79]),
      "+f"(d[80]), "+f"(d[81]), "+f"(d[82]), "+f"(d[83]), "+f"(d[84]), "+f"(d[85]), "+f"(d[86]), "+f"(d[87]),
      "+f"(d[88]), "+f"(d[89]), "+f"(d[90]), "+f"(d[91]), "+f"(d[92]), "+f"(d[93]), "+f"(d[94]), "+f"(d[95]),
      "+f"(d[96]), "+f"(d[97]), "+f"(d[98]), "+f"(d[99]), "+f"(d[100]), "+f"(d[101]), "+f"(d[102]), "+f"(d[103]),
      "+f"(d[104]), "+f"(d[105]), "+f"(d[106]), "+f"(d[107]), "+f"(d[108]), "+f"(d[109]), "+f"(d[110]), "+f"(d[111]),
      "+f"(d[112]), "+f"(d[113]), "+f"(d[114]), "+f"(d[115]), "+f"(d[116]), "+f"(d[117]), "+f"(d[118]), "+f"(d[119]),
      "+f"(d[120]), "+f"(d[121]), "+f"(d[122]), "+f"(d[123]), "+f"(d[124]), "+f"(d[125]), "+f"(d[126]), "+f"(d[127])
    : "r"(da), "r"(db), "n"(OA), "n"(OB));
}

template <int OA, int OB> DEVI void wgmma_acc(float (&d)[64], uint32_t da, uint32_t db) {
  asm volatile("{\n.reg .pred p;\n.reg .b32 la, lb;\n.reg .b64 da, db;\nsetp.ne.b32 p, 1, 0;\n"
    "add.u32 la, %64, %66;\nadd.u32 lb, %65, %67;\nmov.b64 da, {la, 0x40000040};\nmov.b64 db, {lb, 0x40000040};\n"
    "wgmma.mma_async.sync.aligned.m64n128k16.f32.bf16.bf16 {"
    "%0,%1,%2,%3,%4,%5,%6,%7,%8,%9,%10,%11,%12,%13,%14,%15,"
    "%16,%17,%18,%19,%20,%21,%22,%23,%24,%25,%26,%27,%28,%29,%30,%31,"
    "%32,%33,%34,%35,%36,%37,%38,%39,%40,%41,%42,%43,%44,%45,%46,%47,"
    "%48,%49,%50,%51,%52,%53,%54,%55,%56,%57,%58,%59,%60,%61,%62,%63"
    "}, da, db, p, 1, 1, 0, 1;\n}"
    : "+f"(d[0]), "+f"(d[1]), "+f"(d[2]), "+f"(d[3]), "+f"(d[4]), "+f"(d[5]), "+f"(d[6]), "+f"(d[7]),
      "+f"(d[8]), "+f"(d[9]), "+f"(d[10]), "+f"(d[11]), "+f"(d[12]), "+f"(d[13]), "+f"(d[14]), "+f"(d[15]),
      "+f"(d[16]), "+f"(d[17]), "+f"(d[18]), "+f"(d[19]), "+f"(d[20]), "+f"(d[21]), "+f"(d[22]), "+f"(d[23]),
      "+f"(d[24]), "+f"(d[25]), "+f"(d[26]), "+f"(d[27]), "+f"(d[28]), "+f"(d[29]), "+f"(d[30]), "+f"(d[31]),
      "+f"(d[32]), "+f"(d[33]), "+f"(d[34]), "+f"(d[35]), "+f"(d[36]), "+f"(d[37]), "+f"(d[38]), "+f"(d[39]),
      "+f"(d[40]), "+f"(d[41]), "+f"(d[42]), "+f"(d[43]), "+f"(d[44]), "+f"(d[45]), "+f"(d[46]), "+f"(d[47]),
      "+f"(d[48]), "+f"(d[49]), "+f"(d[50]), "+f"(d[51]), "+f"(d[52]), "+f"(d[53]), "+f"(d[54]), "+f"(d[55]),
      "+f"(d[56]), "+f"(d[57]), "+f"(d[58]), "+f"(d[59]), "+f"(d[60]), "+f"(d[61]), "+f"(d[62]), "+f"(d[63])
    : "r"(da), "r"(db), "n"(OA), "n"(OB));
}


struct Ctx {
  uint32_t desc_a, desc_b;
  uint4* halo_out;
  uint32_t bars, orow, kx, v_st, v_ld0, v_ld1, tag;
  int wg, w4, warp, lane;
  bool elected, first;
};
struct Att {
  uint32_t k[16];
  uint32_t v[16];
  uint32_t qlo[8], qhi[8];
};

template <int OA, int OB, bool FIRST = false, int PART = 0, int NR> DEVI void issue_at(float (&acc)[NR], const Ctx& c) {
  constexpr int A = OA >> 4, B = OB >> 4;
  if (!FIRST) fence_acc(acc);
  wgmma_fence();
  if constexpr (PART != 2) {
    if constexpr (FIRST) wgmma_set<A, B>(acc, c.desc_a, c.desc_b);
    else wgmma_acc<A, B>(acc, c.desc_a, c.desc_b);
  }
  if constexpr (PART != 1) {
    wgmma_acc<A + 2, B + 128>(acc, c.desc_a, c.desc_b);
    wgmma_acc<A + 4, B + 256>(acc, c.desc_a, c.desc_b);
    wgmma_acc<A + 6, B + 384>(acc, c.desc_a, c.desc_b);
  }
  wgmma_commit();
}
template <int KB, int PART = 0, int NR> DEVI void issue(float (&acc)[NR], const Ctx& c) {
  issue_at<(KB & 3) * STAGE, (KB & 3) * STAGE, KB == 0, PART>(acc, c);
}
DEVI void release(const Ctx& c, int s) {
  if (c.elected) mbar_arrive(c.bars + B_EMPTY + 8 * s);
}
DEVI void wait_full(const Ctx& c, int kb) { mbar_wait(c.bars + B_FULL + 8 * (kb & 3), (kb >> 2) & 1); }
template <int KB, bool ORDERED = false, int NR> DEVI void step(float (&acc)[NR], const Ctx& c) {
  if (ORDERED && c.wg == 1) named_sync(2, 256);
  wait_full(c, KB);
  issue<KB>(acc, c);
  if (ORDERED && c.wg == 0) named_arrive(2, 256);
  wgmma_wait<1>();
  fence_acc(acc);
  release(c, (KB + 3) & 3);
}
template <int KB0, int KB1, int NR> DEVI void steps(float (&acc)[NR], const Ctx& c) {
  if constexpr (KB0 < KB1) {
    step<KB0>(acc, c);
    steps<KB0 + 1, KB1>(acc, c);
  }
}
template <int KB, int NR> DEVI void open_gap(float (&acc)[NR], const Ctx& c) {
  wait_full(c, KB + 1);
  wgmma_wait<0>();
  fence_acc(acc);
  release(c, KB & 3);
  issue<KB + 1, 1>(acc, c);
  wait_full(c, KB + 1);
}
template <int KB, int NR> DEVI void close_gap(float (&acc)[NR], const Ctx& c, float dep0, float dep1) {
  named_sync_after(1, 256, __float_as_uint(dep0) | __float_as_uint(dep1));
  issue<KB + 1, 2>(acc, c);
}

template <int NR, bool PREV, int W1, int SP, int KEND> DEVI void mainloop(float (&acc)[NR], const Ctx& c, Att& a, int tp) {
  issue<0>(acc, c);
  if constexpr (!PREV) {
    steps<1, KEND>(acc, c);
  } else {
    constexpr int KA = W1 + 1 + SP, KE = KA + 1, KV = KE + SP, W2 = KV + 1, KO = W2 + 1 + SP;
    const int lane = c.lane, qg = lane >> 2, qc = (lane & 3) * 2;
    const uint32_t tpar = tp & 1;
    if (c.w4 == 3 && c.halo_out) {
      uint4* dst = c.halo_out + tp * (4 * 2 * 192);
      st_pkt(dst, a.k[1], a.k[3], a.k[5], c.tag);
      st_pkt(dst + 32, a.k[7], a.k[9], a.k[11], c.tag);
      st_pkt(dst + 64, a.k[13], a.k[15], a.v[1], c.tag);
      st_pkt(dst + 96, a.v[3], a.v[5], a.v[7], c.tag);
      st_pkt(dst + 128, a.v[9], a.v[11], a.v[13], c.tag);
      st_pkt(dst + 160, a.v[15], 0u, 0u, c.tag);
    }
    step<1>(acc, c);
    mbar_wait(c.bars + B_OEMPTY + 8 * c.wg, tpar ^ 1);
    if (c.w4 < 3) {
      stsm_x4(c.kx + 1024, a.k[1], a.k[3], a.k[5], a.k[7]);
      stsm_x4((c.kx + 1024) ^ 64, a.k[9], a.k[11], a.k[13], a.k[15]);
    }
#pragma unroll
    for (int j = 0; j < 4; j++) stsm_x4(c.v_st ^ (j * 32), a.v[4 * j], a.v[4 * j + 1], a.v[4 * j + 2], a.v[4 * j + 3]);
    __syncwarp();
    if (lane == 0 && c.w4 < 3) mbar_arrive(c.bars + B_XBAR + 8 * (c.warp + 1));
    steps<2, W1 + 1>(acc, c);
    uint32_t kp[8];
    mbar_wait(c.bars + B_XBAR + 8 * c.warp, tpar);
    ldsm_x4(c.kx, &kp[0]);
    ldsm_x4(c.kx ^ 64, &kp[4]);
    open_gap<W1>(acc, c);
    float sc[4][4], sd[4][4];
#pragma unroll
    for (int h = 0; h < 2; h++) {
      mma_16816(sc[2 + h], a.k[8 * h], a.k[8 * h + 1], a.k[8 * h + 2], a.k[8 * h + 3], a.qhi[4 * h], a.qhi[4 * h + 1]);
      mma_16816(sc[h], a.k[8 * h], kp[4 * h], a.k[8 * h + 2], kp[4 * h + 1], a.qlo[4 * h], a.qlo[4 * h + 1]);
    }
#pragma unroll
    for (int h = 0; h < 2; h++) {
      mma_16816(sd[2 + h], a.k[8 * h + 4], a.k[8 * h + 5], a.k[8 * h + 6], a.k[8 * h + 7], a.qhi[4 * h + 2], a.qhi[4 * h + 3]);
      mma_16816(sd[h], a.k[8 * h + 4], kp[4 * h + 2], a.k[8 * h + 6], kp[4 * h + 3], a.qlo[4 * h + 2], a.qlo[4 * h + 3]);
    }
    close_gap<W1>(acc, c, sc[2][0], sc[0][0]);
    steps<W1 + 2, KA + 1>(acc, c);
    wait_full(c, KA + 1);
#pragma unroll
    for (int i = 0; i < 4; i++) fence_acc(sc[i]);
#pragma unroll
    for (int i = 0; i < 4; i++)
#pragma unroll
      for (int j = 0; j < 4; j++) sc[i][j] += sd[i][j];
    if (c.first) sc[0][2] = sc[0][3] = sc[1][2] = sc[1][3] = -INFINITY;
    const bool f0 = qg > qc, f1 = qg > qc + 1;
    float y0[4], y1[4], m[4];
#pragma unroll
    for (int i = 0; i < 4; i++) {
      const bool g0 = i < 2 ? !f0 : f0, g1 = i < 2 ? !f1 : f1;
      const uint32_t x = movm_t(scale_logits(pack_bf16(g0 ? sc[i][0] : sc[i][2], g1 ? sc[i][1] : sc[i][3])));
      y0[i] = bf_lo(x);
      y1[i] = bf_hi(x);
      m[i] = fmaxf(y0[i], y1[i]);
    }
#pragma unroll
    for (int i = 0; i < 4; i++) m[i] = fmaxf(m[i], __shfl_xor_sync(0xffffffffu, m[i], 1));
#pragma unroll
    for (int i = 0; i < 4; i++) m[i] = fmaxf(m[i], __shfl_xor_sync(0xffffffffu, m[i], 2));
    step<KE>(acc, c);
#pragma unroll
    for (int i = 0; i < 4; i++) {
      y0[i] = ex2((y0[i] - m[i]) * LOG2E);
      y1[i] = ex2((y1[i] - m[i]) * LOG2E);
      m[i] = y0[i] + y1[i];
    }
#pragma unroll
    for (int i = 0; i < 4; i++) m[i] += __shfl_xor_sync(0xffffffffu, m[i], 1);
#pragma unroll
    for (int i = 0; i < 4; i++) m[i] += __shfl_xor_sync(0xffffffffu, m[i], 2);
    uint32_t vt[8][4];
    if (SP) {
      steps<KE + 1, KV + 1>(acc, c);
#pragma unroll
      for (int i = 0; i < 8; i++) ldsm_x4_t((i < 4 ? c.v_ld0 : c.v_ld1) ^ ((i & 3) * 32), vt[i]);
    }
    step<W2>(acc, c);
    if (!SP) {
#pragma unroll
      for (int i = 0; i < 8; i++) ldsm_x4_t((i < 4 ? c.v_ld0 : c.v_ld1) ^ ((i & 3) * 32), vt[i]);
    }
    const uint32_t m_early = (qc > qg ? 0x0000ffffu : 0u) | (qc + 1 > qg ? 0xffff0000u : 0u);
    uint32_t pe[4], pl[4];
#pragma unroll
    for (int i = 0; i < 4; i++) {
      const float rs = rcp(m[i]);
      const uint32_t pp = pack_bf16(y0[i] * rs, y1[i] * rs);
      pe[i] = pp & m_early;
      pl[i] = pp & ~m_early;
      asm volatile("" : "+r"(pe[i]), "+r"(pl[i]));
    }
    open_gap<W2>(acc, c);
    float o[8][4];
#pragma unroll
    for (int i = 0; i < 8; i++) mma_16816(o[i], vt[i][0], vt[i][1], vt[i][2], vt[i][3], pe[i >> 1], pl[i >> 1]);
    close_gap<W2>(acc, c, o[0][0], o[1][0]);
    steps<W2 + 2, KO + 1>(acc, c);
    wait_full(c, KO + 1);
#pragma unroll
    for (int i = 0; i < 4; i++)
      stsm_x4_t((c.orow + (i >> 1) * 1024) ^ ((i & 1) * 64), pack_bf16(o[2 * i][0], o[2 * i][1]), pack_bf16(o[2 * i][2], o[2 * i][3]),
                pack_bf16(o[2 * i + 1][0], o[2 * i + 1][1]), pack_bf16(o[2 * i + 1][2], o[2 * i + 1][3]));
    fence_async_smem();
    __syncwarp();
    if (lane == 0) mbar_arrive(c.bars + B_OFULL + 8 * c.wg);
    steps<KO + 1, KEND>(acc, c);
  }
}

#define GET_WORK()                                                  \
  int bid_;                                                         \
  asm volatile("mov.u32 %0, %%ctaid.x;" : "=r"(bid_));              \
  int cl = bid_ >> 1;                                               \
  {                                                                 \
    const int c_ = cl - 4, d_ = cl - 36, q_ = (d_ * 37) >> 8;       \
    const int lo_ = (c_ & 7) * 8 + (c_ >> 3);                       \
    const int hi_ = d_ * 8 - q_ * 55 + 12;                          \
    cl = cl < 4 ? cl + 4 : cl < 36 ? lo_ : hi_;                     \
  }                                                                 \
  const int r = 2 * (cl >> 2) + (bid_ & 1);           \
  const int g = cl & 3;                            \
  const int br = r >> 4, rb = r & 15;                               \
  (void)br; (void)rb; (void)g

constexpr int W1_G1 = 4, W1_G2 = 2;
constexpr int POLL_KB = 1;
static_assert(W1_G1 <= POLL_KB + 3, "the helper must not miss the barrier phase it waits for");

__global__ void __cluster_dims__(2, 1, 1) __launch_bounds__(384, 1) fused_kernel(const __grid_constant__ Maps maps) {
  extern __shared__ __align__(1024) uint8_t smem_raw[];
  const uint32_t base = smem_u32(smem_raw);
  const uint32_t bars = base + BAR_OFF;
  const int warp = threadIdx.x >> 5, lane = threadIdx.x & 31;

  if (warp == 0 && elect_one()) {
    GET_WORK();
    mbar_init(bars + B_FULL, 1);
    mbar_init_fence();
    mbar_expect_tx(bars + B_FULL, 40960);
    tma_load_3d(base, &maps.x[br], bars + B_FULL, 0, rb * 64, 0);
    tma_load_3d(base + 16384, &maps.wqkv[br], bars + B_FULL, g * 64, 0, 0);
  }
  if (warp >= 8) {
    asm volatile("setmaxnreg.dec.sync.aligned.u32 %0;" ::"n"(REG_AUX));
    GET_WORK();
    named_sync(0, 384);
    if (warp == 8) {
      if (lane == 0) {
        for (int i = 1; i < 64; i++) {
          const int s = i & 3, kb = i & 15, hp = (i >> 4) * 4 + g;
          const uint32_t sa = base + s * STAGE, full = bars + B_FULL + 8 * s;
          mbar_wait(bars + B_EMPTY + 8 * s, ((i >> 2) & 1) ^ 1);
          mbar_expect_tx(full, 40960);
          tma_load_3d(sa, &maps.x[br], full, kb * 64, rb * 64, 0);
          tma_load_3d(sa + 16384, &maps.wqkv[br], full, hp * 64, kb * 64, 0);
        }
        for (int kb = 0; kb < 16; kb++) {
          const int s = kb & 3;
          const uint32_t sa = base + s * STAGE, full = bars + B_FULL + 8 * s;
          if (kb == 14) {
            mbar_wait(bars + B_OEMPTY, 1);
            mbar_wait(bars + B_OEMPTY + 8, 1);
            mbar_expect_tx(bars + B_LAST, 32768);
            tma_load_2d(base + O_OFF, &maps.o_ld, bars + B_LAST, 15 * 64, r * 128);
            tma_load_3d(base + O_OFF + 16384, &maps.wo_half[br], bars + B_LAST, 0, 15 * 64, g * 4);
          }
          mbar_wait(bars + B_EMPTY + 8 * s, ((kb >> 2) & 1) ^ 1);
          if (kb == 15) {
            mbar_expect_tx(full, 16384);
            tma_load_3d(sa + 32768, &maps.wo_half[br], full, 0, kb * 64, g * 4 + 2);
            break;
          }
          mbar_expect_tx(full, STAGE);
          tma_load_3d(sa + 16384, &maps.wo[br], full, 0, kb * 64, g * 4);
          if (s == 0) mbar_wait(bars + B_OREADY + 2 * kb, 0);
          tma_load_2d(sa, &maps.o_ld, full, kb * 64, r * 128);
        }
      }
    } else if (warp == 11) {
      if (lane == 0) {
        const unsigned e = (unsigned)(atomicAdd(&g_ticket, 1ull) / NCTA);
        asm volatile("st.shared.u32 [%0], %1;" ::"r"(bars + EPOCH_SLOT), "r"(e) : "memory");
        mbar_arrive(bars + B_EPOCH);
        prefetch_map(&maps.wo[br]);
        prefetch_map(&maps.wo_half[br]);
        prefetch_map(&maps.o_ld);
        prefetch_map(&maps.o_st);
        prefetch_map(&maps.out);
      }
      mbar_wait(bars + B_EPOCH, 0);
      const unsigned target = 2u * (lds32(bars + EPOCH_SLOT) + 1u);
      for (int t = 0; t < 4; t++) {
        mbar_wait(bars + B_OSENT + 8 * t, 0);
        unsigned spins = 0;
        while (__any_sync(0xffffffffu, ld_acquire(&g_o_flag[r * 16 + t * 4 + (lane & 3)]) != target) && ++spins < (1u << 22)) {}
        if (lane == 0) {
          fence_async_global();
          mbar_arrive(bars + B_OREADY + 8 * t);
        }
      }
    } else {
      const int p = warp - 9;
      mbar_wait(bars + B_EPOCH, 0);
      const unsigned tag = lds32(bars + EPOCH_SLOT) + 1u;
      const uint32_t moff = (lane & 7) * 128 + ((((uint32_t)lane >> 3) ^ (lane & 7)) << 4);
      const uint32_t kh = base + KX_OFF + p * 4096 + moff, vh = base + VH_OFF + p * 1024 + moff;
      for (int t = 0; t < 4; t++) {
        const int hp = t * 4 + g;
        uint4 k[6];
        if (rb != 0) {
          const uint4* src = g_halo + (((r - 1) * 16 + hp) * 2 + p) * 192 + lane;
          mbar_wait(bars + B_XBAR + 8 * (p * 4 + 1), t & 1);
          if (t < 3) mbar_wait(bars + B_EMPTY + 8 * POLL_KB, 0);
          unsigned spins = 0;
          bool ok;
          do {
            ok = true;
#pragma unroll
            for (int i = 0; i < 6; i++) { k[i] = ld_pkt(src + i * 32); ok = ok && k[i].w == tag; }
          } while (!ok && ++spins < (1u << 22));
          __syncwarp();
        } else {
#pragma unroll
          for (int i = 0; i < 6; i++) k[i] = make_uint4(0u, 0u, 0u, 0u);
        }
        stsm_x4(kh, k[0].x, k[0].y, k[0].z, k[1].x);
        stsm_x4(kh ^ 64, k[1].y, k[1].z, k[2].x, k[2].y);
        stsm_x4(vh, k[2].z, k[3].x, k[3].y, k[3].z);
        stsm_x4(vh ^ 64, k[4].x, k[4].y, k[4].z, k[5].x);
        __syncwarp();
        if (lane == 0) {
          mbar_arrive(bars + B_XBAR + 8 * (p * 4));
          mbar_wait(bars + B_OFULL + 8 * p, t & 1);
          tma_store_2d(&maps.o_st, base + O_OFF + p * 8192, hp * 64, r * 128 + p * 64);
          bulk_commit();
          bulk_wait_read();
          mbar_arrive(bars + B_OEMPTY + 8 * p);
          if (p == 0) mbar_arrive(bars + B_OSENT + 8 * t);
          bulk_wait_all();
          red_add(&g_o_flag[r * 16 + hp], 1u);
        }
        __syncwarp();
      }
    }
  } else {
    if (threadIdx.x == 32) {
      if (base & 1023) __trap();
      for (int s = 1; s < STAGES; s++) mbar_init(bars + B_FULL + 8 * s, 1);
      for (int s = 0; s < STAGES; s++) mbar_init(bars + B_EMPTY + 8 * s, 2);
      for (int i = 0; i < 8; i++) mbar_init(bars + B_XBAR + 8 * i, 1);
      for (int p = 0; p < 2; p++) { mbar_init(bars + B_OFULL + 8 * p, 4); mbar_init(bars + B_OEMPTY + 8 * p, 1); }
      for (int i = 0; i < 4; i++) { mbar_init(bars + B_OREADY + 8 * i, 1); mbar_init(bars + B_OSENT + 8 * i, 1); }
      mbar_init(bars + B_EPOCH, 1);
      mbar_init(bars + B_LAST, 1);
      mbar_init_fence();
    }
    __syncwarp();
    asm volatile("setmaxnreg.inc.sync.aligned.u32 %0;" ::"n"(REG_MMA));
    named_sync(0, 384);
    {
      float dm[96];
      wgmma_fence();
      wgmma_set<0, 0>(dm, desc_lo(base + O_OFF, 16), desc_lo(base + O_OFF + 8192, 2048));
      wgmma_commit();
      wgmma_wait<0>();
      fence_acc(dm);
      if (__float_as_uint(dm[0]) == 0x7fc12345u) asm volatile("st.shared.u32 [%0], %1;" ::"r"(bars + SINK), "r"(0) : "memory");
    }
    GET_WORK();
    Ctx c;
    c.wg = __reduce_or_sync(0xffffffffu, warp >> 2);
    const int wg = c.wg, w4 = warp & 3;
    c.w4 = w4;
    c.lane = lane;
    c.warp = warp;
    c.bars = bars;
    c.first = rb == 0 && w4 == 0;
    c.elected = (threadIdx.x & 127) == 0;
    c.desc_a = desc_lo(base + wg * 8192, 16);
    c.desc_b = desc_lo(base + 16384, 8192);
    c.halo_out = rb != 15 ? g_halo + ((r * 16 + g) * 2 + wg) * 192 + lane : nullptr;
    const uint32_t rx = (lane & 7) * 128, x7 = lane & 7;
    const uint32_t moff = rx + ((((uint32_t)lane >> 3) ^ x7) << 4);
    const uint32_t v_lo = base + O_OFF + warp * 2048, v_hi = v_lo + 1024, v_pr = w4 == 0 ? base + VH_OFF + wg * 1024 : v_lo - 1024;
    c.orow = v_lo + moff;
    c.kx = base + KX_OFF + warp * 1024 + moff;
    c.v_st = ((lane & 8) ? v_hi : v_lo) + rx + ((((uint32_t)lane >> 4) ^ x7) << 4);
    const uint32_t ld16 = rx + (((((uint32_t)lane >> 3) & 1) ^ x7) << 4);
    c.v_ld0 = ((lane & 16) ? v_lo : v_pr) + ld16;
    c.v_ld1 = ((lane & 16) ? v_hi : v_lo) + ld16;
    Att a;
    {
      float acc[96];
#pragma unroll 1
      for (int t = 0; t < 4; t++) {
        if (t == 0) {
          wait_full(c, 0);
          mainloop<96, false, 0, 0, 12>(acc, c, a, 0);
          mbar_wait(bars + B_EPOCH, 0);
          c.tag = lds32(bars + EPOCH_SLOT) + 1u;
        } else {
          mainloop<96, true, W1_G1, 1, 12>(acc, c, a, t - 1);
        }
        steps<12, 15>(acc, c);
        step<15, true>(acc, c);
        wait_full(c, 0);
        wgmma_wait<0>();
        fence_acc(acc);
        release(c, 3);
#pragma unroll
        for (int j = 0; j < 16; j++) {
          a.k[j] = pack_bf16(acc[32 + 2 * j], acc[32 + 2 * j + 1]);
          a.v[j] = pack_bf16(acc[64 + 2 * j], acc[64 + 2 * j + 1]);
        }
#pragma unroll
        for (int j = 0; j < 8; j++) {
          a.qlo[j] = pack_bf16(acc[4 * j], acc[4 * j + 1]);
          a.qhi[j] = pack_bf16(acc[4 * j + 2], acc[4 * j + 3]);
        }
      }
    }
    {
      float acc[128];
      mainloop<128, true, W1_G2, 0, 11>(acc, c, a, 3);
      const uint32_t st_off = w4 * 2048 + (lane & 15) * 128, st_hi = lane >> 4;
      auto store_half = [&](const float (&h)[64], int half, uint32_t dst) {
#pragma unroll
        for (int pn = 0; pn < 2; pn++) {
#pragma unroll
          for (int j = 0; j < 4; j++) {
            const float* v = &h[pn * 32 + j * 8];
            stsm_x4(dst + pn * 8192 + st_off + (((j * 2 + st_hi) ^ x7) << 4), pack_bf16(v[0], v[1]), pack_bf16(v[2], v[3]),
                    pack_bf16(v[4], v[5]), pack_bf16(v[6], v[7]));
          }
          fence_async_smem();
          named_sync(6 + wg, 128);
          if (c.elected) {
            tma_store_3d(&maps.out, dst + pn * 8192, br * 1024 + g * 256 + (half * 2 + pn) * 64, rb * 64, wg);
            bulk_commit();
          }
        }
      };
      step<11, true>(acc, c);
      wait_full(c, 12);
      wait_full(c, 13);
      wgmma_wait<0>();
      fence_acc(acc);
      release(c, 3);
      float hl[64], hr[64];
#pragma unroll
      for (int i = 0; i < 64; i++) asm volatile("mov.b32 %0, %1;" : "=f"(hl[i]) : "f"(acc[i]));
      if (wg == 1) named_sync(5, 256);
      issue<12>(hl, c);
      issue<13>(hl, c);
      mbar_wait(bars + B_LAST, 0);
      issue_at<O_OFF, O_OFF>(hl, c);
      wait_full(c, 14);
      issue<14>(hl, c);
      named_arrive(wg == 0 ? 5 : 3, 256);
#pragma unroll
      for (int i = 0; i < 64; i++) asm volatile("mov.b32 %0, %1;" : "=f"(hr[i]) : "f"(acc[64 + i]));
      mbar_wait(bars + B_EMPTY + 24, 0);
      wgmma_wait<0>();
      fence_acc(hl);
      release(c, 0);
      store_half(hl, 0, base + 3 * STAGE + wg * 16384);
      named_sync(3 + wg, 256);
      issue_at<0, 16384>(hr, c);
      issue_at<STAGE, STAGE + 16384>(hr, c);
      issue_at<2 * STAGE, 2 * STAGE + 16384>(hr, c);
      wait_full(c, 15);
      issue_at<O_OFF, 3 * STAGE + 16384>(hr, c);
      if (wg == 0) named_arrive(4, 256);
      mbar_wait(bars + B_EMPTY, 1);
      wgmma_wait<0>();
      fence_acc(hr);
      store_half(hr, 1, base + wg * STAGE + 16384);
      if (c.elected) bulk_wait_read();
    }
  }
}

typedef CUresult (*EncodeFn)(CUtensorMap*, CUtensorMapDataType, cuuint32_t, void*, const cuuint64_t*, const cuuint64_t*, const cuuint32_t*,
                             const cuuint32_t*, CUtensorMapInterleave, CUtensorMapSwizzle, CUtensorMapL2promotion, CUtensorMapFloatOOBfill);

void encode(EncodeFn fn, CUtensorMap* m, const void* ptr, int rank, const cuuint64_t* dims, const cuuint64_t* strides, const cuuint32_t* box) {
  const cuuint32_t es[3] = {1, 1, 1};
  fn(m, CU_TENSOR_MAP_DATA_TYPE_BFLOAT16, rank, const_cast<void*>(ptr), dims, strides, box, es, CU_TENSOR_MAP_INTERLEAVE_NONE,
     CU_TENSOR_MAP_SWIZZLE_128B, CU_TENSOR_MAP_L2_PROMOTION_L2_128B, CU_TENSOR_MAP_FLOAT_OOB_FILL_NONE);
}

}

extern "C" void kernel_launch(void* const* d_in, const int* in_sizes, int n_in, void* d_out, int out_size) {
  (void)in_sizes; (void)n_in; (void)out_size;
  void* fnp = nullptr;
  cudaDriverEntryPointQueryResult qr;
  cudaGetDriverEntryPoint("cuTensorMapEncodeTiled", &fnp, cudaEnableDefault, &qr);
  EncodeFn fn = (EncodeFn)fnp;
  void* o_ptr = nullptr;
  cudaGetSymbolAddress(&o_ptr, g_o);
  Maps maps;
  for (int b = 0; b < 2; b++) {
    {
      const cuuint64_t d[3] = {1024, 1024, 2}, st[2] = {4096, 2048};
      const cuuint32_t bx[3] = {64, 64, 2};
      encode(fn, &maps.x[b], d_in[3 * b + 0], 3, d, st, bx);
    }
    {
      const cuuint64_t d[3] = {1024, 1024, 3}, st[2] = {6144, 2048};
      const cuuint32_t bx[3] = {64, 64, 3};
      encode(fn, &maps.wqkv[b], d_in[3 * b + 1], 3, d, st, bx);
    }
    {
      const cuuint64_t d[3] = {64, 1024, 16}, st[2] = {2048, 128};
      const cuuint32_t bx[3] = {64, 64, 4}, bh[3] = {64, 64, 2};
      encode(fn, &maps.wo[b], d_in[3 * b + 2], 3, d, st, bx);
      encode(fn, &maps.wo_half[b], d_in[3 * b + 2], 3, d, st, bh);
    }
  }
  {
    const cuuint64_t d[2] = {1024, 4096}, st[1] = {2048};
    const cuuint32_t bl[2] = {64, 128}, bs[2] = {64, 64};
    encode(fn, &maps.o_ld, o_ptr, 2, d, st, bl);
    encode(fn, &maps.o_st, o_ptr, 2, d, st, bs);
  }
  {
    const cuuint64_t d[3] = {2048, 1024, 2}, st[2] = {8192, 4096};
    const cuuint32_t bx[3] = {64, 64, 1};
    encode(fn, &maps.out, d_out, 3, d, st, bx);
  }
  cudaFuncSetAttribute(fused_kernel, cudaFuncAttributeMaxDynamicSharedMemorySize, SMEM_BYTES);
  fused_kernel<<<NCTA, 384, SMEM_BYTES>>>(maps);
}
```
